```python
import torch

def _softmax(x, axis=-1):
    return torch.softmax(x, dim=axis)
def _gelu(x):
    return torch.nn.functional.gelu(x, approximate="tanh")
def _silu(x):
    return torch.nn.functional.silu(x)
def _sigmoid(x):
    return torch.sigmoid(x)
def _layernorm(x, axis=-1, eps=1e-5):
    m = x.mean(dim=axis, keepdim=True)
    v = x.var(dim=axis, keepdim=True, unbiased=False)
    return (x - m) / torch.sqrt(v + eps)
def _scatter_add(tgt, idx, src, axis=0):
    return tgt.clone().index_add_(axis, idx, src)
def _segment_sum(src, seg, n):
    out = torch.zeros((n,) + src.shape[1:], dtype=src.dtype)
    return out.index_add_(0, seg, src)
def _pad(x, pw):
    flat = tuple(v for pair in reversed(pw) for v in pair)
    return torch.nn.functional.pad(x, flat)

kernel_name = 'sequential_preLN__linear_kernel_hedgehog__dense_activation_gelu__prompt'

def setup_inputs():

    _w = (lambda a: (lambda t: t.to(torch.bfloat16) if t.is_floating_point() else t)(torch.as_tensor(a)))
    def _A_setup():
        B, S, D, H = 1, 2048, 576, 32
        Dh = D // H
        return {
            "x": _w((lambda *s: torch.randn(*s, dtype=torch.bfloat16) * 0.05)(B, S, D)),
            "wqkv": _w((lambda *s: torch.randn(*s, dtype=torch.bfloat16) * 0.2)(D, 3 * D)),
            "w_phi": _w((lambda *s: torch.randn(*s, dtype=torch.bfloat16) * 0.2)(H, Dh, Dh) * (Dh ** -0.5)),
            "wo": _w((lambda *s: torch.randn(*s, dtype=torch.bfloat16) * 0.05)(D, D)),
        }
    _A_in = _A_setup()

    def _B_setup():
        B, S, D, F = 1, 2048, 576, 4608
        return {
            "x": _w((lambda *s: torch.randn(*s, dtype=torch.bfloat16) * 0.05)(B, S, D)),
            "w1": _w((lambda *s: torch.randn(*s, dtype=torch.bfloat16) * 3.2)(D, F) * (D ** -0.5)),
            "b1": _w((lambda *s: torch.randn(*s, dtype=torch.bfloat16) * 0.1)(F) * 0.01),
            "w2": _w((lambda *s: torch.randn(*s, dtype=torch.bfloat16) * 0.1)(F, D) * (F ** -0.5)),
            "b2": _w((lambda *s: torch.randn(*s, dtype=torch.bfloat16) * 0.1)(D) * 0.01),
        }
    _B_in = _B_setup()

    return {
        "A_x": _A_in["x"],
        "A_wqkv": _A_in["wqkv"],
        "A_w_phi": _A_in["w_phi"],
        "A_wo": _A_in["wo"],
        "B_x": _B_in["x"],
        "B_w1": _B_in["w1"],
        "B_b1": _B_in["b1"],
        "B_w2": _B_in["w2"],
        "B_b2": _B_in["b2"],
    }

def reference(A_x, A_wqkv, A_w_phi, A_wo, B_x, B_w1, B_b1, B_w2, B_b2):
    def _A_ref(x, wqkv, w_phi, wo):
        B, S, D = x.shape
        H = 32; Dh = D // H
        qkv = (lambda x, *d: x.permute(*d))((x @ wqkv).reshape(B, S, 3, H, Dh), 2, 0, 3, 1, 4)
        q, k, v = qkv[0], qkv[1], qkv[2]
        pq = torch.einsum("bhsd,hdf->bhsf", q, w_phi)
        pk = torch.einsum("bhsd,hdf->bhsf", k, w_phi)
        phi_q = torch.concatenate([_softmax(pq, axis=-1), _softmax(-pq, axis=-1)], axis=-1)
        phi_k = torch.concatenate([_softmax(pk, axis=-1), _softmax(-pk, axis=-1)], axis=-1)
        kv = torch.einsum("bhsf,bhsd->bhfd", phi_k, v)
        z  = torch.einsum("bhsf->bhf", phi_k)
        num = torch.einsum("bhqf,bhfd->bhqd", phi_q, kv)
        den = torch.einsum("bhqf,bhf->bhq", phi_q, z)[..., None] + 1e-6
        o = num / den
        return (lambda x, *d: x.permute(*d))(o, 0, 2, 1, 3).reshape(B, S, D) @ wo

    def _B_ref(x, w1, b1, w2, b2):
        h = torch.einsum("bsd,df->bsf", x, w1) + b1
        h = _gelu(h)
        return torch.einsum("bsf,fd->bsd", h, w2) + b2

    x = A_x
    h = x + _A_ref(_layernorm(x, axis=-1), A_wqkv, A_w_phi, A_wo)
    h2 = h + _B_ref(_layernorm(h, axis=-1), B_w1, B_b1, B_w2, B_b2)
    return h2
```

```cpp
#include <cuda_runtime.h>
#include <cuda.h>
#include <cuda_bf16.h>
#include <stdint.h>

namespace {

constexpr int D_ = 576, F_ = 4608;

constexpr uint32_t SB        = 1024;
constexpr uint32_t RING      = SB;
constexpr uint32_t STAGE     = 12288;
constexpr uint32_t STG       = RING + 6 * STAGE;
constexpr uint32_t SLAB      = 73728;
constexpr uint32_t REMQ      = STG;
constexpr uint32_t BPHI      = STG + 20480;
constexpr uint32_t XV        = BPHI + 11520 + 2048;
constexpr uint32_t BNUM      = STG + SLAB;
constexpr uint32_t PK        = BNUM + 25344;
constexpr uint32_t PKG       = 2080, PKS = 18752;
static_assert(PK + 2 * PKS <= STG + 2 * SLAB, "smem");
constexpr uint32_t REMO      = STG + 2 * SLAB;
constexpr uint32_t B1T       = REMO;
constexpr uint32_t BARS      = REMO + 10240;
constexpr uint32_t FULL = BARS, EMPTY = BARS + 48, SEG = BARS + 96, KVB = BARS + 192, RDY = BARS + 200, X0 = BARS + 224, XB = BARS + 232;
constexpr uint32_t SMEM_END  = BARS + 320;
constexpr uint32_t SMEM_BYTES = SMEM_END - SB;
static_assert(SMEM_BYTES <= 232448, "smem");

constexpr float GA = 0.3292034911525734f;
constexpr float GK = 2.423681954311584f;
constexpr float GINV = 1.5188174288475842f;

__device__ __align__(1024) float4   g_kv[8 * 17 * 768];
__device__ __align__(1024) uint4    g_oh[2][16 * 8 * 36 * 32];
__device__ __align__(1024) float4   g_st[128 * 8 * 8];
__device__ __align__(1024) uint4    g_part[16 * 9 * 8 * 8 * 128];
__device__ __align__(1024) float4   g_b1t[128 * 180];
__device__ __align__(1024) unsigned g_epoch[128 * 32];

__host__ __device__ constexpr uint64_t cdesc(uint32_t addr, uint32_t lbo, uint32_t sbo, uint32_t swz) {
  return (uint64_t)((addr & 0x3FFFF) >> 4) | ((uint64_t)(lbo >> 4) << 16) | ((uint64_t)(sbo >> 4) << 32) | ((uint64_t)swz << 62);
}
__device__ __forceinline__ void mbar_init(uint32_t bar, uint32_t cnt) { asm volatile("mbarrier.init.shared::cta.b64 [%0], %1;" :: "r"(bar), "r"(cnt) : "memory"); }
__device__ __forceinline__ void mbar_expect_tx(uint32_t bar, uint32_t bytes) { asm volatile("mbarrier.arrive.expect_tx.shared::cta.b64 _, [%0], %1;" :: "r"(bar), "r"(bytes) : "memory"); }
__device__ __forceinline__ void mbar_arrive(uint32_t bar) { asm volatile("mbarrier.arrive.shared::cta.b64 _, [%0];" :: "r"(bar) : "memory"); }
__device__ __forceinline__ void mbar_wait(uint32_t bar, uint32_t parity) {
  asm volatile("{ .reg .pred p;\n"
               "WAIT_%=: mbarrier.try_wait.parity.shared::cta.b64 p, [%0], %1; @!p bra WAIT_%=; }" :: "r"(bar), "r"(parity) : "memory");
}
__device__ __forceinline__ void chk(uint32_t& bad, uint32_t w, uint32_t tag) { asm("lop3.b32 %0, %0, %1, %2, 0xF6;" : "+r"(bad) : "r"(w), "r"(tag)); }
__device__ __forceinline__ uint32_t settag(uint32_t w, uint32_t tag) { uint32_t r; asm("lop3.b32 %0, %1, 0xfffffffe, %2, 0xEA;" : "=r"(r) : "r"(w), "r"(tag)); return r; }
__device__ __forceinline__ bool elect_one() {
  uint32_t p; asm volatile("{ .reg .pred P; elect.sync _|P, 0xffffffff; selp.u32 %0, 1, 0, P; }" : "=r"(p)); return p;
}
__device__ __forceinline__ void tma_2d(uint32_t dst, const CUtensorMap* m, int c0, int c1, uint32_t bar) {
  asm volatile("cp.async.bulk.tensor.2d.shared::cluster.global.mbarrier::complete_tx::bytes [%0], [%1, {%3, %4}], [%2];" :: "r"(dst), "l"(m), "r"(bar), "r"(c0), "r"(c1) : "memory");
}
__device__ __forceinline__ uint32_t bar_or(uint32_t id, uint32_t v) {
  uint32_t r; asm volatile("{ .reg .pred p; setp.ne.b32 p, %2, 0; bar.red.or.pred p, %1, 128, p; vote.sync.any.pred p, p, 0xffffffff; selp.u32 %0, 1, 0, p; }" : "=r"(r) : "r"(id), "r"(v) : "memory"); return r;
}
__device__ __forceinline__ void bar_wg(uint32_t id) { asm volatile("bar.sync %0, 128;" :: "r"(id) : "memory"); }
__device__ __forceinline__ void bulk_g2s(uint32_t dst, const void* src, uint32_t bytes, uint32_t bar) {
  asm volatile("cp.async.bulk.shared::cluster.global.mbarrier::complete_tx::bytes [%0], [%1], %2, [%3];" :: "r"(dst), "l"(src), "r"(bytes), "r"(bar) : "memory");
}
__device__ __forceinline__ void cp_async16(uint32_t dst, const void* src) { asm volatile("cp.async.cg.shared.global [%0], [%1], 16;" :: "r"(dst), "l"(src) : "memory"); }
__device__ __forceinline__ void ldsm4(uint32_t a, uint32_t& x, uint32_t& y, uint32_t& z, uint32_t& w) { asm volatile("ldmatrix.sync.aligned.m8n8.x4.shared.b16 {%0, %1, %2, %3}, [%4];" : "=r"(x), "=r"(y), "=r"(z), "=r"(w) : "r"(a) : "memory"); }
__device__ __forceinline__ uint32_t lds32(uint32_t a) { uint32_t v; asm volatile("ld.shared.b32 %0, [%1];" : "=r"(v) : "r"(a) : "memory"); return v; }
__device__ __forceinline__ void lds64(uint32_t a, uint32_t& x, uint32_t& y) { asm volatile("ld.shared.v2.b32 {%0, %1}, [%2];" : "=r"(x), "=r"(y) : "r"(a) : "memory"); }
__device__ __forceinline__ uint32_t ldg32(const void* p) { uint32_t v; asm volatile("ld.relaxed.gpu.global.b32 %0, [%1];" : "=r"(v) : "l"(p) : "memory"); return v; }
__device__ __forceinline__ uint32_t hfma2(uint32_t a, uint32_t b, uint32_t c) { uint32_t r; asm volatile("fma.rn.bf16x2 %0, %1, %2, %3;" : "=r"(r) : "r"(a), "r"(b), "r"(c)); return r; }
__device__ __forceinline__ uint64_t opaque(uint64_t v) { uint64_t r; asm volatile("mov.b64 %0, %1;" : "=l"(r) : "l"(v)); return r; }
__device__ __forceinline__ int tid_opaque() { int r; asm volatile("mov.u32 %0, %%tid.x;" : "=r"(r)); return r; }
__device__ __forceinline__ void delay_clk(uint32_t n) { const uint32_t t0 = clock(); while ((uint32_t)clock() - t0 < n) __nanosleep(20); }
__device__ __forceinline__ float quad_sum(float v) { v += __shfl_xor_sync(0xffffffff, v, 1); return v + __shfl_xor_sync(0xffffffff, v, 2); }
__device__ __forceinline__ void wg_fence() { asm volatile("wgmma.fence.sync.aligned;" ::: "memory"); }
__device__ __forceinline__ void wg_commit() { asm volatile("wgmma.commit_group.sync.aligned;" ::: "memory"); }
template <int N> __device__ __forceinline__ void wg_wait() { asm volatile("wgmma.wait_group.sync.aligned %0;" :: "n"(N) : "memory"); }
__device__ __forceinline__ void proxy_fence() { asm volatile("fence.proxy.async.shared::cta;" ::: "memory"); }
template <int ID, int N> __device__ __forceinline__ void bar_sync() { asm volatile("bar.sync %0, %1;" :: "n"(ID), "n"(N) : "memory"); }
template <int ID, int N> __device__ __forceinline__ void bar_arrive() { asm volatile("bar.arrive %0, %1;" :: "n"(ID), "n"(N) : "memory"); }
__device__ __forceinline__ uint32_t pack_bf16(float lo, float hi) { uint32_t r; asm("cvt.rn.bf16x2.f32 %0, %1, %2;" : "=r"(r) : "f"(hi), "f"(lo)); return r; }
__device__ __forceinline__ float bf_lo(uint32_t v) { return __uint_as_float(v << 16); }
__device__ __forceinline__ float bf_hi(uint32_t v) { return __uint_as_float(v & 0xffff0000u); }
__device__ __forceinline__ uint32_t hadd2(uint32_t a, uint32_t b) { uint32_t r; asm("add.rn.bf16x2 %0, %1, %2;" : "=r"(r) : "r"(a), "r"(b)); return r; }
__device__ __forceinline__ uint32_t hsub2(uint32_t a, uint32_t b) { uint32_t r; asm volatile("sub.rn.bf16x2 %0, %1, %2;" : "=r"(r) : "r"(a), "r"(b)); return r; }
__device__ __forceinline__ float ex2(float x) { float r; asm("ex2.approx.ftz.f32 %0, %1;" : "=f"(r) : "f"(x)); return r; }
__device__ __forceinline__ float rsq(float x) { float r; asm("rsqrt.approx.ftz.f32 %0, %1;" : "=f"(r) : "f"(x)); return r; }
__device__ __forceinline__ float rcp(float x) { float r; asm("rcp.approx.ftz.f32 %0, %1;" : "=f"(r) : "f"(x)); return r; }
__device__ __forceinline__ float gelu_z(float z) { float u = z * fmaf(z, z, GK); float t; asm("tanh.approx.f32 %0, %1;" : "=f"(t) : "f"(u)); return fmaf(z, t, z); }
__device__ __forceinline__ void sts32(uint32_t a, uint32_t v) { asm volatile("st.shared.b32 [%0], %1;" :: "r"(a), "r"(v) : "memory"); }
__device__ __forceinline__ void sts64(uint32_t a, uint32_t x, uint32_t y) { asm volatile("st.shared.v2.b32 [%0], {%1, %2};" :: "r"(a), "r"(x), "r"(y) : "memory"); }
__device__ __forceinline__ void sts128(uint32_t a, uint32_t x, uint32_t y, uint32_t z, uint32_t w) { asm volatile("st.shared.v4.b32 [%0], {%1, %2, %3, %4};" :: "r"(a), "r"(x), "r"(y), "r"(z), "r"(w) : "memory"); }
__device__ __forceinline__ void lds128(uint32_t a, uint32_t& x, uint32_t& y, uint32_t& z, uint32_t& w) { asm volatile("ld.shared.v4.b32 {%0, %1, %2, %3}, [%4];" : "=r"(x), "=r"(y), "=r"(z), "=r"(w) : "r"(a) : "memory"); }
__device__ __forceinline__ void ldg128(const void* p, uint32_t& x, uint32_t& y, uint32_t& z, uint32_t& w) { asm volatile("ld.relaxed.gpu.global.v4.b32 {%0, %1, %2, %3}, [%4];" : "=r"(x), "=r"(y), "=r"(z), "=r"(w) : "l"(p) : "memory"); }
__device__ __forceinline__ void stg128(void* p, uint32_t x, uint32_t y, uint32_t z, uint32_t w) { asm volatile("st.relaxed.gpu.global.v4.b32 [%0], {%1, %2, %3, %4};" :: "l"(p), "r"(x), "r"(y), "r"(z), "r"(w) : "memory"); }
__device__ __forceinline__ void mma_ones(float (&d)[4], uint32_t a0, uint32_t a1, uint32_t a2, uint32_t a3) {
  asm volatile("mma.sync.aligned.m16n8k16.row.col.f32.bf16.bf16.f32 {%0, %1, %2, %3}, {%4, %5, %6, %7}, {%8, %8}, {%0, %1, %2, %3};"
      : "+f"(d[0]), "+f"(d[1]), "+f"(d[2]), "+f"(d[3]) : "r"(a0), "r"(a1), "r"(a2), "r"(a3), "r"(0x3f803f80u));
}
template <int N> __device__ __forceinline__ void pin(float* d) {
  #pragma unroll
  for (int i = 0; i < N; i++) asm volatile("" : "+f"(d[i]) :: "memory");
}
__device__ __forceinline__ uint32_t gather5(uint32_t d, uint32_t e, const void* p, uint32_t tag) {
  uint32_t bad;
  asm volatile("{ .reg .b32 v<5>;\n"
               "cp.async.cg.shared.global [%1], [%3], 16; cp.async.cg.shared.global [%1+256], [%3+1216], 16;\n"
               "cp.async.cg.shared.global [%1+512], [%3+2432], 16; cp.async.cg.shared.global [%1+768], [%3+3648], 16;\n"
               "cp.async.cg.shared.global [%2], [%3+4864], 16; cp.async.wait_all;\n"
               "ld.shared.b32 v0, [%1]; ld.shared.b32 v1, [%1+256]; ld.shared.b32 v2, [%1+512]; ld.shared.b32 v3, [%1+768]; ld.shared.b32 v4, [%2];\n"
               "lop3.b32 v0, v0, v1, %4, 0x7E; lop3.b32 v2, v2, v3, %4, 0x7E; xor.b32 v4, v4, %4; lop3.b32 %0, v0, v2, v4, 0xFE; }"
               : "=r"(bad) : "r"(d), "r"(e), "l"(p), "r"(tag) : "memory");
  return bad;
}
__device__ __forceinline__ void mma_add(float* d, const float* c, uint32_t a0, uint32_t a1, uint32_t eye) {
  asm("mma.sync.aligned.m16n8k8.row.col.f32.bf16.bf16.f32 {%0, %1, %2, %3}, {%4, %5}, {%6}, {%7, %8, %9, %10};"
      : "=f"(d[0]), "=f"(d[1]), "=f"(d[2]), "=f"(d[3]) : "r"(a0), "r"(a1), "r"(eye), "f"(c[0]), "f"(c[1]), "f"(c[2]), "f"(c[3]));
}
__device__ __forceinline__ void wg_rs_n64(float* d, uint32_t a0, uint32_t a1, uint32_t a2, uint32_t a3, uint64_t db, int scale_d) {
  asm volatile("{ .reg .pred p; setp.ne.b32 p, %37, 0;\n"
    "wgmma.mma_async.sync.aligned.m64n64k16.f32.bf16.bf16 {%0, %1, %2, %3, %4, %5, %6, %7, %8, %9, %10, %11, %12, %13, %14, %15, %16, %17, %18, %19, %20, %21, %22, %23, %24, %25, %26, %27, %28, %29, %30, %31}, {%32, %33, %34, %35}, %36, p, 1, 1, 1; }"
    : "+f"(d[0]), "+f"(d[1]), "+f"(d[2]), "+f"(d[3]), "+f"(d[4]), "+f"(d[5]), "+f"(d[6]), "+f"(d[7]), "+f"(d[8]), "+f"(d[9]), "+f"(d[10]), "+f"(d[11]), "+f"(d[12]), "+f"(d[13]), "+f"(d[14]), "+f"(d[15]), "+f"(d[16]), "+f"(d[17]), "+f"(d[18]), "+f"(d[19]), "+f"(d[20]), "+f"(d[21]), "+f"(d[22]), "+f"(d[23]), "+f"(d[24]), "+f"(d[25]), "+f"(d[26]), "+f"(d[27]), "+f"(d[28]), "+f"(d[29]), "+f"(d[30]), "+f"(d[31])
    : "r"(a0), "r"(a1), "r"(a2), "r"(a3), "l"(db), "r"(scale_d));
}
__device__ __forceinline__ void wg_rs_n72(float* d, uint32_t a0, uint32_t a1, uint32_t a2, uint32_t a3, uint64_t db, int scale_d) {
  asm volatile("{ .reg .pred p; setp.ne.b32 p, %41, 0;\n"
    "wgmma.mma_async.sync.aligned.m64n72k16.f32.bf16.bf16 {%0, %1, %2, %3, %4, %5, %6, %7, %8, %9, %10, %11, %12, %13, %14, %15, %16, %17, %18, %19, %20, %21, %22, %23, %24, %25, %26, %27, %28, %29, %30, %31, %32, %33, %34, %35}, {%36, %37, %38, %39}, %40, p, 1, 1, 1; }"
    : "+f"(d[0]), "+f"(d[1]), "+f"(d[2]), "+f"(d[3]), "+f"(d[4]), "+f"(d[5]), "+f"(d[6]), "+f"(d[7]), "+f"(d[8]), "+f"(d[9]), "+f"(d[10]), "+f"(d[11]), "+f"(d[12]), "+f"(d[13]), "+f"(d[14]), "+f"(d[15]), "+f"(d[16]), "+f"(d[17]), "+f"(d[18]), "+f"(d[19]), "+f"(d[20]), "+f"(d[21]), "+f"(d[22]), "+f"(d[23]), "+f"(d[24]), "+f"(d[25]), "+f"(d[26]), "+f"(d[27]), "+f"(d[28]), "+f"(d[29]), "+f"(d[30]), "+f"(d[31]), "+f"(d[32]), "+f"(d[33]), "+f"(d[34]), "+f"(d[35])
    : "r"(a0), "r"(a1), "r"(a2), "r"(a3), "l"(db), "r"(scale_d));
}
__device__ __forceinline__ void wg_ss_n88(float* d, uint64_t da, uint64_t db, int scale_d) {
  asm volatile("{ .reg .pred p; setp.ne.b32 p, %46, 0;\n"
    "wgmma.mma_async.sync.aligned.m64n88k16.f32.bf16.bf16 {%0, %1, %2, %3, %4, %5, %6, %7, %8, %9, %10, %11, %12, %13, %14, %15, %16, %17, %18, %19, %20, %21, %22, %23, %24, %25, %26, %27, %28, %29, %30, %31, %32, %33, %34, %35, %36, %37, %38, %39, %40, %41, %42, %43}, %44, %45, p, 1, 1, 0, 0; }"
    : "+f"(d[0]), "+f"(d[1]), "+f"(d[2]), "+f"(d[3]), "+f"(d[4]), "+f"(d[5]), "+f"(d[6]), "+f"(d[7]), "+f"(d[8]), "+f"(d[9]), "+f"(d[10]), "+f"(d[11]), "+f"(d[12]), "+f"(d[13]), "+f"(d[14]), "+f"(d[15]), "+f"(d[16]), "+f"(d[17]), "+f"(d[18]), "+f"(d[19]), "+f"(d[20]), "+f"(d[21]), "+f"(d[22]), "+f"(d[23]), "+f"(d[24]), "+f"(d[25]), "+f"(d[26]), "+f"(d[27]), "+f"(d[28]), "+f"(d[29]), "+f"(d[30]), "+f"(d[31]), "+f"(d[32]), "+f"(d[33]), "+f"(d[34]), "+f"(d[35]), "+f"(d[36]), "+f"(d[37]), "+f"(d[38]), "+f"(d[39]), "+f"(d[40]), "+f"(d[41]), "+f"(d[42]), "+f"(d[43])
    : "l"(da), "l"(db), "r"(scale_d));
}
__device__ __forceinline__ void wg_ss_n72t(float* d, uint64_t da, uint64_t db, int scale_d) {
  asm volatile("{ .reg .pred p; setp.ne.b32 p, %38, 0;\n"
    "wgmma.mma_async.sync.aligned.m64n72k16.f32.bf16.bf16 {%0, %1, %2, %3, %4, %5, %6, %7, %8, %9, %10, %11, %12, %13, %14, %15, %16, %17, %18, %19, %20, %21, %22, %23, %24, %25, %26, %27, %28, %29, %30, %31, %32, %33, %34, %35}, %36, %37, p, 1, 1, 1, 1; }"
    : "+f"(d[0]), "+f"(d[1]), "+f"(d[2]), "+f"(d[3]), "+f"(d[4]), "+f"(d[5]), "+f"(d[6]), "+f"(d[7]), "+f"(d[8]), "+f"(d[9]), "+f"(d[10]), "+f"(d[11]), "+f"(d[12]), "+f"(d[13]), "+f"(d[14]), "+f"(d[15]), "+f"(d[16]), "+f"(d[17]), "+f"(d[18]), "+f"(d[19]), "+f"(d[20]), "+f"(d[21]), "+f"(d[22]), "+f"(d[23]), "+f"(d[24]), "+f"(d[25]), "+f"(d[26]), "+f"(d[27]), "+f"(d[28]), "+f"(d[29]), "+f"(d[30]), "+f"(d[31]), "+f"(d[32]), "+f"(d[33]), "+f"(d[34]), "+f"(d[35])
    : "l"(da), "l"(db), "r"(scale_d));
}


__host__ __device__ constexpr uint64_t rem_off(int k) { return (uint64_t)(((k >> 3) * 2048 + (k & 7) * 16 + 73728 - k * 2048) >> 4) << 16; }
template <int N, class Hook>
__device__ __forceinline__ void mma_issue(float* d, uint32_t (&a)[144], uint64_t ring_desc, uint32_t ph, int wl, Hook hook) {
  const uint64_t db = opaque(ring_desc);
  #pragma unroll
  for (int ks = 0; ks < 6; ks++) {
    mbar_wait(FULL + 8 * ks, ph);
    wg_fence();
    #pragma unroll
    for (int kk = 0; kk < 6; kk++) {
      const int k = ks * 6 + kk;
      if (N == 64) wg_rs_n64(d, a[4 * k], a[4 * k + 1], a[4 * k + 2], a[4 * k + 3], db + k * 128, k != 0);
      else         wg_rs_n72(d, a[4 * k], a[4 * k + 1], a[4 * k + 2], a[4 * k + 3], db + (k * 128 + rem_off(k)), k != 0);
    }
    wg_commit();
    hook(ks);
    if (ks > 0 && ks < 5) { wg_wait<1>(); if (wl == 0) mbar_arrive(EMPTY + 8 * (ks - 1)); }
  }
}
template <int N> __device__ __forceinline__ void mma_finish(float* d, int wl) {
  wg_wait<1>();
  if (wl == 0) mbar_arrive(EMPTY + 8 * 4);
  wg_wait<0>();
  if (wl == 0) mbar_arrive(EMPTY + 8 * 5);
  pin<N / 2>(d);
}
template <int N, class Hook>
__device__ __forceinline__ void mma_block(float* d, uint32_t (&a)[144], uint64_t ring_desc, uint32_t ph, int wl, Hook hook) {
  mma_issue<N>(d, a, ring_desc, ph, wl, hook);
  mma_finish<N>(d, wl);
}

template <int OFF>
__device__ __forceinline__ void dual_softmax(const float* p, float L2E, uint32_t pb, uint32_t pe) {
  float mx = fmaxf(p[OFF], p[OFF + 1]), mn = fminf(p[OFF], p[OFF + 1]);
  #pragma unroll
  for (int j = 1; j < 9; j++) { mx = fmaxf(mx, fmaxf(p[4 * j + OFF], p[4 * j + OFF + 1])); mn = fminf(mn, fminf(p[4 * j + OFF], p[4 * j + OFF + 1])); }
  uint32_t last[2];
  #pragma unroll
  for (int h = 0; h < 2; h++) {
    const float c = h ? mn * L2E : -mx * L2E, l = h ? -L2E : L2E;
    float e[18], s0 = 0.f, s1 = 0.f;
    #pragma unroll
    for (int j = 0; j < 9; j++) { e[2 * j] = ex2(fmaf(p[4 * j + OFF], l, c)); e[2 * j + 1] = ex2(fmaf(p[4 * j + OFF + 1], l, c)); s0 += e[2 * j]; s1 += e[2 * j + 1]; }
    const float r = rcp(s0 + s1);
    #pragma unroll
    for (int q = 0; q < 2; q++)
      sts128(pb + (4 * h + 2 * q) * PKG, pack_bf16(e[8 * q] * r, e[8 * q + 1] * r), pack_bf16(e[8 * q + 2] * r, e[8 * q + 3] * r),
             pack_bf16(e[8 * q + 4] * r, e[8 * q + 5] * r), pack_bf16(e[8 * q + 6] * r, e[8 * q + 7] * r));
    last[h] = pack_bf16(e[16] * r, e[17] * r);
  }
  sts64(pe, last[0], last[1]);
}

struct Params {
  CUtensorMap m[6];
  const __nv_bfloat16 *x, *wqkv, *wphi, *wo, *w1, *b1, *w2, *b2;
  __nv_bfloat16* out;
  uint64_t ring_desc, pass_desc[4];
};

__global__ void __launch_bounds__(384, 1) fused_block_kernel(const __grid_constant__ Params P) {
  const int tile = (blockIdx.x >> 2) & 15, g = 4 * (blockIdx.x >> 6) + (blockIdx.x & 3);
  const int odd = g & 1;
  const int warp = __shfl_sync(0xffffffff, threadIdx.x >> 5, 0);

  if (warp == 8) {
    if (elect_one()) {
      #pragma unroll 1
      for (int i = 0; i < 3; i++) {
        mbar_init(XB + 8 * i, 1); mbar_expect_tx(XB + 8 * i, 49152);
        asm volatile("cp.async.bulk.tensor.3d.shared::cluster.global.mbarrier::complete_tx::bytes [%0], [%1, {%5, %3, %4}], [%2];"
                     :: "r"(STG + i * 49152), "l"(&P.m[4]), "r"(XB + 8 * i), "r"(tile * 128), "r"(3 * i), "r"(0) : "memory");
      }
      #pragma unroll
      for (int i = 0; i < 6; i++) { mbar_init(FULL + 8 * i, 1); mbar_init(EMPTY + 8 * i, 2); }
    }
    __syncwarp();
    bar_arrive<1, 320>();
  }
  if (warp == 9) {
    if (elect_one()) {
      #pragma unroll
      for (int i = 0; i < 12; i++) mbar_init(SEG + 8 * i, 1);
      mbar_init(KVB, 3); mbar_init(RDY + 16, 1); mbar_init(X0, 8); mbar_init(RDY + 8, 3);
    }
    __syncwarp();
    bar_arrive<1, 320>();
  }
  auto rem_load4 = [&](uint32_t buf, int col) {
    const uint32_t h = threadIdx.x & 127, c0 = (threadIdx.x >> 7) * 4;
    if (h < 80 - 4 * c0) {
      const char* p = reinterpret_cast<const char*>(P.wqkv + col + 72 * g + 64 - 64 * odd) + ((h >> 4) * 128 + (h & 15) + 16 * c0) * (6 * D_);
      #pragma unroll
      for (uint32_t c = 0; c < 4; c++) cp_async16((buf + h * 128 + (h & 7) * 16) ^ ((c0 + c) << 4), p + c * (96 * D_));
    }
    asm volatile("cp.async.commit_group;" ::: "memory");
  };
  if (warp < 8) {
    delay_clk(800);
    rem_load4(REMO, D_);
  }
  if (warp >= 8) {
    asm volatile("setmaxnreg.dec.sync.aligned.u32 24;");
    if (warp > 8) {
      const uint32_t ht = threadIdx.x - 288;
      const uint32_t rrow = (ht >> 4) * 128 + (ht & 15), rcnt = ht < 64 ? 128 : ht < 80 ? 64 : 0;
      auto rem_load = [&](uint32_t buf, const __nv_bfloat16* w, uint32_t pitch) {
        const char* p = reinterpret_cast<const char*>(w + 72 * g + 64 - 64 * odd) + rrow * pitch;
        const uint32_t d = buf + ht * 128 + (ht & 7) * 16;
        #pragma unroll 1
        for (uint32_t c = 0; c < rcnt; c += 16, p += 16 * pitch) cp_async16(d ^ c, p);
      };
      auto ready = [&](uint32_t bar) { proxy_fence(); __syncwarp(); if (elect_one()) mbar_arrive(bar); };
      const unsigned epoch = g_epoch[blockIdx.x * 32];
      if (warp == 9 && elect_one()) {
        #pragma unroll 1
        for (int i = 0; i < 6; i++) asm volatile("prefetch.tensormap [%0];" :: "l"(&P.m[i]) : "memory");
      }
      bar_sync<4, 96>();
      const uint32_t nt = epoch & 1;
      char* kvo = reinterpret_cast<char*>(g_kv + (g * 17 + tile) * 768);
      #pragma unroll
      for (int i = 0; i < 8; i++) stg128(kvo + ht * 16 + i * 1536, nt, nt, nt, nt);
      if (ht < 64) {
        if (ht < 24) stg128(g_kv + (g * 17 + 16) * 768 + tile * 24 + ht, nt, nt, nt, nt);
        char* p = reinterpret_cast<char*>(g_oh[0]) + (tile * (2 * SLAB) + (9 * g >> 1) * 2048 + (odd ? 384 : 8192 + 128)) + ((ht >> 5) * SLAB + ((ht >> 3) & 3) * 512 + (ht & 7) * 16);
        stg128(p, nt, nt, nt, nt); stg128(p + sizeof(g_oh[0]), nt, nt, nt, nt);
        stg128(reinterpret_cast<char*>(g_st + tile * 512 + 8 * g) + ((ht >> 3) * 1024 + (ht & 7) * 16), nt, nt, nt, nt);
      }
      mbar_wait(X0, 0);
      rem_load(REMQ, P.wqkv + 2 * D_, 6 * D_);
      if (ht < 80) {
        const uint32_t hd = ht / 18, ad = BPHI + (ht >= 72 || !odd ? ht : ht < 8 ? ht + 64 : ht - 8) * 16;
        const uint32_t* src = reinterpret_cast<const uint32_t*>(P.wphi) + (72u * g + ht) * 9u;
        #pragma unroll 1
        for (uint32_t j = 0; j < 9; j++) {
          #pragma unroll
          for (uint32_t i = 1; i < 4; i++) sts32(ad + j * 1280 + ((hd + i) & 3) * 4, 0u);
          asm volatile("cp.async.ca.shared.global [%0], [%1], 4, %2;" :: "r"(ad + j * 1280 + (hd & 3) * 4), "l"(ht < 72 ? src + j : src - 72), "r"(ht < 72 ? 4 : 0) : "memory");
        }
      }
      if (ht < 64) {
        #pragma unroll
        for (int i = 0; i < 4; i++) sts128(XV - 2048 + (i >> 1) * 20480 + (i & 1) * 1024 + ht * 16, 0x3f803f80u, 0x3f803f80u, 0x3f803f80u, 0x3f803f80u);
      }
      asm volatile("cp.async.wait_all;" ::: "memory");
      ready(RDY + 8);
      #pragma unroll 1
      for (uint32_t i = ht * 16; i < 25344; i += 1536) sts128(BNUM + i, 0u, 0u, 0u, 0u);
      if (ht < 72) {
        const uint2* bp = reinterpret_cast<const uint2*>(P.b1) + 144 * g + ((ht >> 1) * 4 + (ht & 1));
        const uint2 u = __ldg(bp), v = __ldg(bp + 2);
        float4* d = g_b1t + blockIdx.x * 180 + 2 * ht;
        d[0] = make_float4(bf_lo(u.x) * GA, bf_hi(u.x) * GA, bf_lo(v.x) * GA, bf_hi(v.x) * GA);
        d[1] = make_float4(bf_lo(u.y) * GA, bf_hi(u.y) * GA, bf_lo(v.y) * GA, bf_hi(v.y) * GA);
      }
      if (ht >= 64) {
        const uint2 u = __ldg(reinterpret_cast<const uint2*>(P.b2) + (ht < 80 ? 16 * g - 64 : 48) + ht);
        g_b1t[blockIdx.x * 180 + 84 + ht] = make_float4(bf_lo(u.x), bf_hi(u.x), bf_lo(u.y), bf_hi(u.y));
      }
      asm volatile("fence.proxy.async.global;" ::: "memory");
      mbar_wait(X0, 1);
      #pragma unroll 1
      for (int i = 0; i < 2; i++) rem_load(i ? REMO : REMQ + 10240, i ? P.wo : P.wqkv, i ? 2 * D_ : 6 * D_);
      asm volatile("cp.async.wait_all;" ::: "memory");
      proxy_fence();
      bar_sync<2, 352>();
      if (warp == 9 && elect_one()) {
        mbar_expect_tx(RDY + 16, 18432);
        tma_2d(XV, &P.m[5], 72 * g, tile * 128, RDY + 16);
        g_epoch[blockIdx.x * 32] = epoch + 1;
      }
      {
        const uint32_t n = min(ht, 87u), tt = n < 72 ? n / 18 : ((n - 72) >> 3) * 2 + (n & 1);
        const float4* src = g_kv + (g * 17 + 16) * 768 + (n < 72 ? n + (tt & 2) : 19 * (tt & 2) + 36 + (tt & 1));
        const uint32_t dst = BNUM + (n >= 72 || !odd ? n >> 3 : n < 8 ? 8 : (n >> 3) - 1) * 2304 + (n & 7) * 16 + (tt >> 1) * 1152;
        delay_clk(2200);
        #pragma unroll 1
        for (int i = 0; i < 0x40000 && (gather5(dst + (tt & 1) * 128, dst + 1024, src, nt ^ 1) & 1); i++) {}
      }
      ready(KVB);
      bar_sync<11, 352>();
      #pragma unroll 1
      for (uint32_t u = ht; u < 128; u += 96) {
        const uint32_t o16 = ((g >> 2) * 512 + (g & 3) * 32) + ((u >> 5) * 128 + (u & 31));
        const uint4* src = g_part + (tile * 9 + 8) * 8192 + o16;
        const uint32_t sa = STG + 28 * 2048 + u * 16;
        #pragma unroll 1
        for (int m = 0; m < 8; m++) cp_async16(sa + m * 2048, src + m * 1024);
        asm volatile("cp.async.wait_all;" ::: "memory");
        float d[8] = {0.f, 0.f, 0.f, 0.f, 0.f, 0.f, 0.f, 0.f};
        uint32_t w[4];
        #pragma unroll 1
        for (int m = 0; m < 8; m++, src += 1024) {
          lds128(sa + m * 2048, w[0], w[1], w[2], w[3]);
          for (int n = 0; !((w[0] ^ nt) & 1) && n < 0x40000; n++) ldg128(src, w[0], w[1], w[2], w[3]);
          #pragma unroll
          for (int i = 0; i < 4; i++) { d[2 * i] += bf_lo(w[i]); d[2 * i + 1] += bf_hi(w[i]); }
        }
        ldg128(g_oh[1] + (tile * 2 + (g >> 2)) * (SLAB / 16) + 4096 + (g & 3) * 32 + ((u >> 5) * 128 + (u & 31)), w[0], w[1], w[2], w[3]);
        uint32_t* op = reinterpret_cast<uint32_t*>(P.out) + (tile * 128 + g * 16) * 288 + 256 + (((u & 31) >> 2) * 288 + (u >> 5) * 8 + (u & 3));
        #pragma unroll
        for (int i = 0; i < 4; i++) {
          uint32_t b0, b1;
          lds64(B1T + 2624 + (u >> 5) * 64 + (i >> 1) * 32 + (u & 3) * 8, b0, b1);
          op[(i & 1) * (8 * 288) + (i >> 1) * 4] = pack_bf16(fmaf(d[2 * i], GINV, __uint_as_float(b0) + bf_lo(w[i])), fmaf(d[2 * i + 1], GINV, __uint_as_float(b1) + bf_hi(w[i])));
        }
      }
    } else {
      if (elect_one()) {
        #pragma unroll 1
        for (int blk = 0; blk < 22; blk++) {
          int mi, c0, r0 = 0;
          if (blk < 4)       { mi = blk == 3; c0 = (blk < 2 ? D_ + D_ * blk : 0) + 72 * g + 8 * odd; }
          else if (blk < 13) { mi = 2; c0 = 576 * g + 64 * (blk - 4); }
          else               { mi = 3; const int n = blk - 13; c0 = 64 * (n == 0 ? 8 : ((g + n) & 7)); r0 = 576 * g; }
          #pragma unroll
          for (int ks = 0; ks < 6; ks++) {
            mbar_wait(EMPTY + 8 * ks, ~blk & 1);
            mbar_expect_tx(FULL + 8 * ks, ks == 5 && blk == 4 ? STAGE + 2880 : STAGE);
            tma_2d(RING + ks * STAGE, &P.m[mi], c0, r0 + 96 * ks, FULL + 8 * ks);
          }
          if (blk == 0 && tile < 6)
            asm volatile("cp.async.bulk.prefetch.tensor.2d.L2.global [%0, {%1, %2}];" :: "l"(&P.m[0]), "r"(c0 + D_), "r"(96 * tile) : "memory");
          if (blk == 4) bulk_g2s(B1T, g_b1t + blockIdx.x * 180, 2880, FULL + 40);
        }
      }
    }
  } else {
    asm volatile("setmaxnreg.inc.sync.aligned.u32 240;");
    const int lane = threadIdx.x & 31, wl = threadIdx.x & 127;
    const int slab = tile * 8 + warp;
    const unsigned epoch = g_epoch[blockIdx.x * 32];
    const uint32_t tag = ~epoch & 1;
    const int wg = warp >> 2;
    const uint32_t wo_ = wg * SLAB + (warp & 3) * 512, sw = STG + wo_;
    const uint32_t sl = sw + lane * 16, sl8 = sw + lane * 8;

    uint32_t a[144];
    float rs0, rs1;
    uint32_t m0p, m1p;
    const uint32_t seg = SEG + wg * 48;
    bar_sync<1, 320>();
    {
      const uint32_t xa = STG + (warp * 16 + (lane & 15)) * 128 + (((lane >> 4) ^ (lane & 7)) << 4);
      float s[4][4] = {};
      #pragma unroll
      for (int k = 0; k < 36; k++) {
        if (k % 12 == 0) mbar_wait(XB + 8 * (k / 12), 0);
        ldsm4((xa ^ ((k & 3) << 5)) + (k >> 2) * 16384, a[4 * k], a[4 * k + 1], a[4 * k + 2], a[4 * k + 3]);
        mma_ones(s[k & 3], a[4 * k], a[4 * k + 1], a[4 * k + 2], a[4 * k + 3]);
      }
      asm volatile("cp.async.wait_group 0;" ::: "memory");
      proxy_fence();
      __syncwarp();
      if (lane == 0) mbar_arrive(X0);
      const float mean0 = ((s[0][0] + s[1][0]) + (s[2][0] + s[3][0])) * (1.f / 576.f), mean1 = ((s[0][2] + s[1][2]) + (s[2][2] + s[3][2])) * (1.f / 576.f);
      m0p = pack_bf16(mean0, mean0); m1p = pack_bf16(mean1, mean1);
      rs0 = mean0 - bf_lo(m0p); rs1 = mean1 - bf_lo(m1p);
    }
    #pragma unroll
    for (int i = 0; i < 72; i++) {
      a[2 * i] = hsub2(a[2 * i], m0p); a[2 * i + 1] = hsub2(a[2 * i + 1], m1p);
    }
    mbar_wait(X0, 0);
    uint32_t xr[20];
    #pragma unroll
    for (int i = 0; i < 20; i++) xr[i] = 0u;
    uint32_t segpar = 0;
    char* gb = reinterpret_cast<char*>(g_oh[0]) + (tile * (2 * SLAB) + wo_);
    #pragma unroll 1
    for (int pass = 0;; pass++) {
      float sq0 = 0.f, sq1 = 0.f, accA[36];
      mma_issue<72>(accA, a, P.pass_desc[pass], pass & 1, wl, [&](int ks) {
        if (pass == 0) {
          uint32_t s[4] = {0u, 0u, 0u, 0u};
          #pragma unroll
          for (int i = 24 * ks; i < 24 * ks + 24; i++) s[i & 3] = hfma2(a[i], a[i], s[i & 3]);
          s[0] = hadd2(s[0], s[2]); s[1] = hadd2(s[1], s[3]);
          sq0 += bf_lo(s[0]) + bf_hi(s[0]); sq1 += bf_lo(s[1]) + bf_hi(s[1]);
        }
      });
      const int tid = tid_opaque(), t = tid & 3, srow = (tid >> 5) * 16 + ((tid & 31) >> 2);
      if (pass == 2 && wg == 0) bar_arrive<3, 256>();
      if (pass == 0) {
        const float q0 = quad_sum(sq0), q1 = quad_sum(sq1);
        rs0 = rsq(fmaxf(q0 * (1.f / 576.f) - rs0 * rs0, 0.f) + 1e-5f);
        rs1 = rsq(fmaxf(q1 * (1.f / 576.f) - rs1 * rs1, 0.f) + 1e-5f);
        mbar_wait(RDY + 8, 0);
      }
      mma_finish<72>(accA, wl);
      if ((pass | lane) == 0) mbar_arrive(X0);
      {
      uint32_t c0[9], c1[9];
      if (pass < 3) {
        if (pass == 1) {
          const uint32_t ad = XV + srow * 16 + 4 * t;
          #pragma unroll
          for (int j = 0; j < 9; j++) {
            const uint32_t aj = ad + (j < 8 ? (j + odd) * 2048 : (8 - 8 * odd) * 2048);
            sts32(aj, pack_bf16(accA[4 * j] * rs0, accA[4 * j + 1] * rs0));
            sts32(aj + 128, pack_bf16(accA[4 * j + 2] * rs1, accA[4 * j + 3] * rs1));
          }
        } else {
          #pragma unroll
          for (int i = 0; i < 18; i++) xr[i] = pack_bf16(accA[2 * i], accA[2 * i + 1]);
        }
        if (pass == 2 || pass == wg) {
          float p[36];
          wg_fence();
          #pragma unroll
          for (int s = 0; s < 5; s++) wg_rs_n72(p, xr[4 * s], xr[4 * s + 1], xr[4 * s + 2], xr[4 * s + 3], cdesc(BPHI + s * 256, 128, 1280, 0), s != 0);
          wg_commit();
          wg_wait<0>();
          pin<36>(p);
          if (pass == 2) {
            mbar_wait(RDY + 16, 0);
            const uint32_t xa = XV + srow * 144 + 4 * t;
            #pragma unroll
            for (int j = 0; j < 9; j++) { const uint32_t aj = xa + (j < 8 ? 16 * (j + odd) : 128 - 128 * odd); xr[2 * j] = lds32(aj); xr[2 * j + 1] = lds32(aj + 8 * 144); }
            if (wg) bar_arrive<9, 256>();
          }
          const uint32_t pb = PK + (t >> 1) * PKS + srow * 16 + (t & 1) * PKG;
          const uint32_t pe = pb + 8 * PKG - (t & 1) * (PKG - 8);
          dual_softmax<0>(p, rs0 * 1.4426950408889634f, pb, pe);
          dual_softmax<2>(p, rs1 * 1.4426950408889634f, pb + 128, pe + 128);
        }
        if (pass == 0) { if (wg) continue; goto next_zero; }
        proxy_fence();
        if (pass == 1) {
          bar_sync<5, 256>();
          {
            const int hp = wg;
            float kv[36];
            const uint64_t da = cdesc(XV - 2048, 128, 2048, 0) + (uint64_t)(hp * (5 * 2048 >> 4)), db = cdesc(PK, 128, PKG, 0) + (uint64_t)(hp * (PKS >> 4));
            wg_fence();
            #pragma unroll
            for (int s = 0; s < 8; s++) wg_ss_n72t(kv, da + s * 16, db + s * 16, s != 0);
            wg_commit();
            wg_wait<0>();
            pin<36>(kv);
            const uint64_t kvb = opaque(reinterpret_cast<uint64_t>(g_kv + (g * 17 + tile) * 768 + hp * 76) + t * 8);
            #pragma unroll
            for (int r = 0; r < 2; r++) {
              int m = (srow & 63) + 8 * r - 8 + 4 * hp;
              const bool ok = hp ? (m >= 0 && m < 38) : (m >= -2 && m < 36);
              if (m < 0) m += 38;
              const bool hs = m >= 18 && m != 36;
              const uint64_t dst = kvb + (uint32_t)(m * 32);
              if (ok) {
                #pragma unroll
                for (int q = 0; q < 5; q++) {
                  const bool alt = q < 4 ? hs : (t >> 1) != (int)hs;
                  const float x = !alt ? kv[8 * q + 2 * r] : q < 4 ? kv[(8 * q + 4 + 2 * r) % 36] : 0.f, y = !alt ? kv[8 * q + 1 + 2 * r] : q < 4 ? kv[(8 * q + 5 + 2 * r) % 36] : 0.f;
                  asm volatile("st.relaxed.gpu.global.v2.b32 [%0], {%1, %2};" :: "l"(dst + 2432 * q), "r"(settag(__float_as_uint(x), tag)), "f"(y) : "memory");
                }
              }
            }
          }
          bar_sync<2, 352>();
          if (wg) {
            const uint32_t f = tile * 48 + (warp & 3) * 16 + (tid & 15);
            if (warp < 7) {
              const float4* src = g_kv + (g * 17 + ((tid & 16) >> 1)) * 768 + min(f, 759u);
              uint32_t v[32], bad;
              int n = 0;
              delay_clk(800);
              do {
                bad = 0;
                #pragma unroll
                for (int i = 0; i < 8; i++) { ldg128(src + i * 768, v[4 * i], v[4 * i + 1], v[4 * i + 2], v[4 * i + 3]); }
                #pragma unroll
                for (int i = 0; i < 16; i++) chk(bad, v[2 * i], tag);
              } while (__any_sync(0xffffffff, bad & 1) && ++n < 0x40000);
              float x[4];
              #pragma unroll
              for (int c = 0; c < 4; c++) {
                x[c] = ((__uint_as_float(v[c]) + __uint_as_float(v[4 + c])) + (__uint_as_float(v[8 + c]) + __uint_as_float(v[12 + c])))
                     + ((__uint_as_float(v[16 + c]) + __uint_as_float(v[20 + c])) + (__uint_as_float(v[24 + c]) + __uint_as_float(v[28 + c])));
                x[c] += __shfl_xor_sync(0xffffffff, x[c], 16);
              }
              const uint32_t lo = pack_bf16(x[0], x[1]), hi = pack_bf16(x[2], x[3]);
              const uint32_t lo2 = __shfl_down_sync(0xffffffff, lo, 1), hi2 = __shfl_down_sync(0xffffffff, hi, 1);
              if (!(tid & 17)) stg128(g_kv + (g * 17 + 16) * 768 + (f >> 1), settag(lo, tag), hi, lo2, hi2);
            }
            bar_sync<3, 256>();
          }
          goto next_zero;
        }
        float nm[44];
        if (wg) bar_sync<8, 256>(); else bar_wg(6);
        mbar_wait(KVB, 0);
        wg_fence();
        #pragma unroll
        for (int b = 0; b < 9; b++)
          wg_ss_n88(nm, cdesc(PK + (b < 5 ? 2 * b * PKG : PKS + (2 * b - 9) * PKG), b == 4 ? PKS - 8 * PKG : PKG, 128, 0) + (uint64_t)(wg * 64),
                    cdesc(BNUM + b * 256, 128, 2304, 0), b != 0);
        wg_commit();
        if (!wg) bar_arrive<8, 256>();
        wg_wait<0>();
        pin<44>(nm);

        float r0[4], r1[4];
        r0[0] = rcp(nm[36] + 1e-6f); r0[1] = rcp(nm[37] + 1e-6f); r0[2] = rcp(nm[40] + 1e-6f); r0[3] = rcp(nm[41] + 1e-6f);
        r1[0] = rcp(nm[38] + 1e-6f); r1[1] = rcp(nm[39] + 1e-6f); r1[2] = rcp(nm[42] + 1e-6f); r1[3] = rcp(nm[43] + 1e-6f);
        #pragma unroll
        for (int j = 0; j < 9; j++) {
          const int h = j == 8 ? 3 : (8 * j) / 18, th = j == 8 ? 4 : (18 * (h + 1) - 8 * j) / 2;
          const bool up = t + 4 * odd >= th;
          const float s0 = th < 8 && up ? r0[(h + 1) & 3] : r0[h], s1 = th < 8 && up ? r1[(h + 1) & 3] : r1[h];
          c0[j] = pack_bf16(nm[4 * j] * s0, nm[4 * j + 1] * s0); c1[j] = pack_bf16(nm[4 * j + 2] * s1, nm[4 * j + 3] * s1);
        }
      } else {
        #pragma unroll
        for (int j = 0; j < 9; j++) { c0[j] = hadd2(xr[2 * j], pack_bf16(accA[4 * j], accA[4 * j + 1])); c1[j] = hadd2(xr[2 * j + 1], pack_bf16(accA[4 * j + 2], accA[4 * j + 3])); }
      }
      if (pass == 3) gb += sizeof(g_oh[0]);
      {
        const int lane = tid & 31;
        char* ob = gb + (9 * g >> 1) * 2048;
        asm volatile("st.relaxed.gpu.global.v2.b32 [%0], {%1, %2};" :: "l"(ob + (odd ? 256 : 8192) + lane * 8), "r"(settag(c0[8], tag)), "r"(c1[8]) : "memory");
        #pragma unroll
        for (int i = 0; i < 4; i++) stg128(ob + (i + odd) * 2048 + lane * 16, settag(c0[2 * i], tag), c1[2 * i], c0[2 * i + 1], c1[2 * i + 1]);
      }
      float4* sp = g_st + slab * 64 + ((tid & 31) >> 2);
      if (pass == 3) {
        const uint32_t pv = __shfl_sync(0xffffffff, __byte_perm(c0[0], c1[0], 0x5410), tid & 28);
        const uint32_t p0 = __byte_perm(pv, 0, 0x1010), p1 = __byte_perm(pv, 0, 0x3232);
        uint32_t s[4] = {0u, 0u, 0u, 0u}, w[4] = {0u, 0u, 0u, 0u};
        #pragma unroll
        for (int j = 0; j < 9; j++) {
          const uint32_t u0 = hsub2(c0[j], p0), u1 = hsub2(c1[j], p1);
          const int i = 2 * (j & 1);
          s[i] = j < 2 ? u0 : hadd2(s[i], u0); s[i + 1] = j < 2 ? u1 : hadd2(s[i + 1], u1);
          w[i] = hfma2(u0, u0, w[i]); w[i + 1] = hfma2(u1, u1, w[i + 1]);
        }
        const float s0 = quad_sum(bf_lo(s[0]) + bf_hi(s[0]) + bf_lo(s[2]) + bf_hi(s[2])) * (1.f / 72.f), s1 = quad_sum(bf_lo(s[1]) + bf_hi(s[1]) + bf_lo(s[3]) + bf_hi(s[3])) * (1.f / 72.f);
        const float w0 = quad_sum(bf_lo(w[0]) + bf_hi(w[0]) + bf_lo(w[2]) + bf_hi(w[2])), w1 = quad_sum(bf_lo(w[1]) + bf_hi(w[1]) + bf_lo(w[3]) + bf_hi(w[3]));
        if (t == 0) stg128(sp + 8 * g, __float_as_uint(bf_lo(pv) + s0), settag(__float_as_uint(fmaf(-72.f * s0, s0, w0)), tag), __float_as_uint(bf_hi(pv) + s1), __float_as_uint(fmaf(-72.f * s1, s1, w1)));
      }
      uint32_t bad;
      do {
        uint32_t u[8] = {0u, 0u, 0u, 0u, 0u, 0u, 0u, 0u};
        if ((warp & 3) == 0 && elect_one()) {
          #pragma unroll
          for (int i = 0; i < 6; i++) mbar_expect_tx(seg + 8 * i, 12288);
        }
        const char* pp = gb + (uint32_t)((9 * (tid & 7) >> 1) * 2048 + ((tid & 1) ? 504 : 8192 + 248));
        for (int np = 0; __any_sync(0xffffffff, (ldg32(pp) ^ tag) & 1) && np < 0x40000; np++) {}
        if (pass == 3) { ldg128(sp + 16 * t, u[0], u[1], u[4], u[5]); ldg128(sp + 16 * t + 8, u[2], u[3], u[6], u[7]); }
        asm volatile("bar.sync %0, %1;" :: "r"((segpar ? 6 : 9) + wg), "r"(segpar ? 128 : 256) : "memory");
        if ((warp & 3) == 0 && elect_one()) {
          #pragma unroll
          for (int i = 0; i < 6; i++) bulk_g2s(sw + i * 12288, gb + i * 12288, 12288, seg + 8 * i);
        }
        if (segpar + wg == 0) bar_arrive<10, 256>();
        if (pass == 3) {
          #pragma unroll 1
          for (int n = 0; n < 0x40000; n++) {
            bad = 0; chk(bad, u[1], tag); chk(bad, u[3], tag);
            if (!__any_sync(0xffffffff, bad & 1)) break;
            ldg128(sp + 16 * t, u[0], u[1], u[4], u[5]);
            ldg128(sp + 16 * t + 8, u[2], u[3], u[6], u[7]);
          }
        }
        const float mean0 = quad_sum(__uint_as_float(u[0]) + __uint_as_float(u[2])) * 0.125f, mean1 = quad_sum(__uint_as_float(u[4]) + __uint_as_float(u[6])) * 0.125f;
        m0p = pack_bf16(mean0, mean0); m1p = pack_bf16(mean1, mean1);
        float d0 = __uint_as_float(u[0]) - mean0, d1 = __uint_as_float(u[2]) - mean0;
        rs0 = quad_sum(fmaf(72.f, d0 * d0 + d1 * d1, __uint_as_float(u[1]) + __uint_as_float(u[3])));
        d0 = __uint_as_float(u[4]) - mean1; d1 = __uint_as_float(u[6]) - mean1;
        rs1 = quad_sum(fmaf(72.f, d0 * d0 + d1 * d1, __uint_as_float(u[5]) + __uint_as_float(u[7])));
        rs0 = rsq(fmaxf(rs0, 0.f) * (1.f / 576.f) + 1e-5f) * GA; rs1 = rsq(fmaxf(rs1, 0.f) * (1.f / 576.f) + 1e-5f) * GA;
        bad = 0;
        #pragma unroll
        for (int k = 0; k < 36; k++) {
          if (k % 6 == 0) mbar_wait(seg + 8 * (k / 6), segpar & 1);
          if (k % 9 == 4) { lds64(sl8 + k * 2048, a[4 * k], a[4 * k + 1]); lds64(sl8 + k * 2048 + 256, a[4 * k + 2], a[4 * k + 3]); }
          else lds128(sl + k * 2048, a[4 * k], a[4 * k + 1], a[4 * k + 2], a[4 * k + 3]);
          if (k % 6 == 5) {
            #pragma unroll
            for (int i = 4 * k - 20; i < 4 * k + 4; i++) {
              if (i % 4 == 0 || i % 36 == 18) chk(bad, a[i], tag);
              a[i] = hsub2(a[i], (i & 1) ? m1p : m0p);
            }
          }
        }
        segpar++;
      } while (bar_or(6 + wg, bad & 1) && segpar < 64);
      if (pass == 3) break;
      continue;
      }
    next_zero:
      #pragma unroll
      for (int i = 0; i < 18; i++) { xr[i] = 0u; asm volatile("" : "+r"(xr[i])); }
    }
    float accA[32], accB[32];
    mma_block<64>(accA, a, P.ring_desc, 0, wl, [](int) {});
    uint32_t b1a = B1T + (lane & 3) * 16, ha = sl;
    uint32_t bn[4];
    lds128(b1a, bn[0], bn[1], bn[2], bn[3]);
    auto gelu_sts = [&](float* d, int c, int p) {
      if (p < 0 || p > 3) return;
      const float b0 = __uint_as_float(bn[0]), b1 = __uint_as_float(bn[1]), b2 = __uint_as_float(bn[2]), b3 = __uint_as_float(bn[3]);
      const float y0 = fmaf(d[8 * p], rs0, b0), y1 = fmaf(d[8 * p + 1], rs0, b1), y2 = fmaf(d[8 * p + 2], rs1, b0), y3 = fmaf(d[8 * p + 3], rs1, b1);
      const float y4 = fmaf(d[8 * p + 4], rs0, b2), y5 = fmaf(d[8 * p + 5], rs0, b3), y6 = fmaf(d[8 * p + 6], rs1, b2), y7 = fmaf(d[8 * p + 7], rs1, b3);
      lds128(b1a + (c * 4 + p + 1) * 64, bn[0], bn[1], bn[2], bn[3]);
      sts128(ha + (c * 4 + p) * 2048, pack_bf16(gelu_z(y0), gelu_z(y1)), pack_bf16(gelu_z(y2), gelu_z(y3)),
             pack_bf16(gelu_z(y4), gelu_z(y5)), pack_bf16(gelu_z(y6), gelu_z(y7)));
    };
    auto reload = [&](int k0, int k1) {
      #pragma unroll
      for (int k = 0; k < 36; k++) if (k >= k0 && k < k1) lds128(sl + k * 2048, a[4 * k], a[4 * k + 1], a[4 * k + 2], a[4 * k + 3]);
    };
    #pragma unroll 1
    for (int it = 0;; it++) {
      mma_block<64>(accB, a, P.ring_desc + (it >> 8), 1, wl,
                [&](int ks) { gelu_sts(accA, 0, ks - 1); if ((ks == 0 || ks == 4) && it == 4) reload(ks ? 32 : 24, ks ? 36 : 32); });
      if (it == 4) break;
      mma_block<64>(accA, a, P.ring_desc + (it >> 8), 0, wl,
                [&](int ks) { gelu_sts(accB, 1, ks == 1 ? 0 : ks == 2 ? 1 : ks == 4 ? 2 : ks == 5 ? 3 : -1);
                              if (ks >= 2 && it == 3) reload(6 * ks - 12, 6 * ks - 6); });
      b1a += 512; ha += 16384;
    }
    uint4* partp = g_part + ((tile * 9 * 8 + g) * 1024 + wg * 512 + (warp & 3) * 32) + lane;
    const uint4* parti = g_part + ((tile * 9 + g) * 8192 + wg * 512 + (warp & 3) * 32) + lane;
    auto fetch = [&](int m) {
      const int src = (g - m) & 7;
      const uint4* p = m ? parti + src * 1024 : reinterpret_cast<const uint4*>(gb) + g * 512 + lane;
      #pragma unroll
      for (int i = 0; i < 4; i++) cp_async16(sl + (4 * m + i) * 2048, p + i * 128);
      asm volatile("cp.async.commit_group;" ::: "memory");
    };
    uint4* pp;
    auto part_store = [&](float* d, int n, int ks) {
      if (ks < 2) {
        if (ks == 0) { pp = partp + (n == 0 ? 8 : ((g + n) & 7)) * 8192; asm volatile("" : "+l"(pp)); }
        #pragma unroll
        for (int p = 2 * ks; p < 2 * ks + 2; p++)
          stg128(pp + p * 128, settag(pack_bf16(d[8 * p], d[8 * p + 1]), tag), pack_bf16(d[8 * p + 2], d[8 * p + 3]),
                 pack_bf16(d[8 * p + 4], d[8 * p + 5]), pack_bf16(d[8 * p + 6], d[8 * p + 7]));
      } else if (ks == 3 && n >= 1) fetch(n - 1);
    };
    #pragma unroll 1
    for (int it = 0;; it++) {
      mma_block<64>(accA, a, P.ring_desc + (it >> 8), 0, wl, [&](int ks) { part_store(accB, 2 * it, ks); });
      mma_issue<64>(accB, a, P.ring_desc + (it >> 8), 1, wl, [&](int ks) { part_store(accA, 2 * it + 1, ks); });
      if (it == 3) break;
      if (it == 0) bar_arrive<11, 352>();
      mma_finish<64>(accB, wl);
    }
    uint32_t w7[16], hr[16], b2v[16];
    auto load7 = [&]() {
      #pragma unroll
      for (int p = 0; p < 4; p++) ldg128(parti + ((g + 1) & 7) * 1024 + p * 128, w7[4 * p], w7[4 * p + 1], w7[4 * p + 2], w7[4 * p + 3]);
    };
    asm volatile("cp.async.wait_group 1;" ::: "memory");
    uint32_t bad;
    int m0 = 7 + (int)(P.ring_desc & 1), tries = 0;
    const uint32_t eye = (lane >> 3) != (lane & 3) ? 0u : (lane & 4) ? 0x3f800000u : 0x00003f80u;
    do {
      #pragma unroll 1
      for (int m = m0; m < 7; m++) { fetch(m); asm volatile("cp.async.wait_group 0;" ::: "memory"); }
      m0 = 0;
      __syncwarp();
      bad = 0;
      uint32_t w[112];
      #pragma unroll
      for (int i = 4; i < 12; i++) lds128(sl + i * 2048, w[4 * i], w[4 * i + 1], w[4 * i + 2], w[4 * i + 3]);
      load7();
      wg_wait<0>();
      pin<32>(accB);
      #pragma unroll
      for (int m = 0; m < 6; m++) {
        #pragma unroll
        for (int i = 4 * m; i < 4 * m + 4; i++) if (i >= 12) lds128(sl + i * 2048, w[4 * i], w[4 * i + 1], w[4 * i + 2], w[4 * i + 3]);
      }
      #pragma unroll
      for (int p = 0; p < 4; p++) {
        const bool split = g == 2 * p + 1;
        lds64((split ? sl8 : sl) + p * 2048, hr[4 * p], hr[4 * p + 1]);
        lds64((split ? sl8 + 256 : sl + 8) + p * 2048, hr[4 * p + 2], hr[4 * p + 3]);
      }
      #pragma unroll
      for (int j = 0; j < 8; j++) lds64(B1T + 2368 + (lane & 3) * 8 + j * 32, b2v[2 * j], b2v[2 * j + 1]);
      #pragma unroll
      for (int m = 0; m < 7; m++) {
        if (m == 4) {
          asm volatile("cp.async.wait_group 0;" ::: "memory");
          #pragma unroll
          for (int i = 24; i < 28; i++) lds128(sl + i * 2048, w[4 * i], w[4 * i + 1], w[4 * i + 2], w[4 * i + 3]);
        }
        #pragma unroll
        for (int j = 0; j < 8; j++) if (m) {
          if (!(j & 1)) chk(bad, w[16 * m + 2 * j], tag);
          mma_add(accA + 4 * j, (m == 1 ? accB : accA) + 4 * j, w[16 * m + 2 * j], w[16 * m + 2 * j + 1], eye);
        }
      }
    } while (__any_sync(0xffffffff, bad & 1) && ++tries < 0x10000);
    #pragma unroll 1
    for (int n = 0; n < 0x40000; n++) {
      bad = 0;
      #pragma unroll
      for (int p = 0; p < 4; p++) chk(bad, w7[4 * p], tag);
      if (!__any_sync(0xffffffff, bad & 1)) break;
      load7();
    }
    #pragma unroll
    for (int j = 0; j < 8; j++) {
      float* d = accA + 4 * j;
      const float b0 = __uint_as_float(b2v[2 * j]), b1 = __uint_as_float(b2v[2 * j + 1]);
      mma_add(d, d, w7[2 * j], w7[2 * j + 1], eye);
      const float c[4] = {b0, b1, b0, b1};
      float e[4];
      mma_add(e, c, hr[2 * j], hr[2 * j + 1], eye);
      hr[2 * j] = pack_bf16(fmaf(d[0], GINV, e[0]), fmaf(d[1], GINV, e[1])); hr[2 * j + 1] = pack_bf16(fmaf(d[2], GINV, e[2]), fmaf(d[3], GINV, e[3]));
    }
    {
      const uint32_t r = lane & 15, oa = sw + 8192 + (r >> 2) * 2048 + (r & 3) * 128 + (((lane >> 4) ^ (lane & 7)) << 4);
      #pragma unroll
      for (int p = 0; p < 4; p++)
        asm volatile("stmatrix.sync.aligned.m8n8.x4.shared.b16 [%0], {%1, %2, %3, %4};" :: "r"(oa ^ (p << 5)), "r"(hr[4 * p]), "r"(hr[4 * p + 1]), "r"(hr[4 * p + 2]), "r"(hr[4 * p + 3]) : "memory");
      __syncwarp();
      char* ob = reinterpret_cast<char*>(P.out) + ((tile * 128 + warp * 16) * 1152 + g * 128) + (uint32_t)((lane >> 3) * 1152 + (lane & 7) * 16);
      #pragma unroll
      for (int i = 0; i < 4; i++) {
        uint32_t x, y, z, w;
        lds128((sl + 8192 + i * 2048) ^ (((lane >> 3) + 4 * (i & 1)) << 4), x, y, z, w);
        stg128(ob + i * 4 * 1152, x, y, z, w);
      }
    }
  }
}

typedef CUresult (*EncodeFn)(CUtensorMap*, CUtensorMapDataType, cuuint32_t, void*, const cuuint64_t*, const cuuint64_t*,
                             const cuuint32_t*, const cuuint32_t*, CUtensorMapInterleave, CUtensorMapSwizzle,
                             CUtensorMapL2promotion, CUtensorMapFloatOOBfill);

void encode2d(EncodeFn fn, CUtensorMap* m, const void* base, uint64_t cols, uint64_t rows, uint32_t bc, uint32_t br) {
  cuuint64_t dims[2] = {cols, rows}, strides[1] = {cols * 2};
  cuuint32_t box[2] = {bc, br}, es[2] = {1, 1};
  fn(m, CU_TENSOR_MAP_DATA_TYPE_BFLOAT16, 2, const_cast<void*>(base), dims, strides, box, es, CU_TENSOR_MAP_INTERLEAVE_NONE,
     bc == 64 ? CU_TENSOR_MAP_SWIZZLE_128B : CU_TENSOR_MAP_SWIZZLE_NONE,
     bc == 64 ? CU_TENSOR_MAP_L2_PROMOTION_L2_128B : CU_TENSOR_MAP_L2_PROMOTION_NONE, CU_TENSOR_MAP_FLOAT_OOB_FILL_NONE);
}

}

extern "C" void kernel_launch(void* const* d_in, const int* in_sizes, int n_in, void* d_out, int out_size) {
  (void)in_sizes; (void)n_in; (void)out_size;
  static EncodeFn fn = nullptr;
  if (!fn) {
    void* p = nullptr; cudaDriverEntryPointQueryResult qr;
    cudaGetDriverEntryPoint("cuTensorMapEncodeTiled", &p, cudaEnableDefault, &qr);
    fn = reinterpret_cast<EncodeFn>(p);
    cudaFuncSetAttribute(fused_block_kernel, cudaFuncAttributeMaxDynamicSharedMemorySize, SMEM_BYTES);
  }
  Params P;
  P.x = (const __nv_bfloat16*)d_in[0]; P.wqkv = (const __nv_bfloat16*)d_in[1]; P.wphi = (const __nv_bfloat16*)d_in[2];
  P.wo = (const __nv_bfloat16*)d_in[3]; P.w1 = (const __nv_bfloat16*)d_in[5]; P.b1 = (const __nv_bfloat16*)d_in[6];
  P.w2 = (const __nv_bfloat16*)d_in[7]; P.b2 = (const __nv_bfloat16*)d_in[8]; P.out = (__nv_bfloat16*)d_out;
  P.ring_desc = cdesc(RING, 8192, 1024, 1);
  for (int i = 0; i < 4; i++) P.pass_desc[i] = cdesc(RING, ((i == 1 || i == 2) ? REMQ + (i - 1) * 10240 : REMO) - RING - 73728, 1024, 1);
  encode2d(fn, &P.m[0], P.wqkv, 3 * D_, D_, 64, 96);
  encode2d(fn, &P.m[1], P.wo, D_, D_, 64, 96);
  encode2d(fn, &P.m[2], P.w1, F_, D_, 64, 96);
  encode2d(fn, &P.m[3], P.w2, D_, F_, 64, 96);
  {
    cuuint64_t dims[3] = {64, 2048, 9}, strides[2] = {D_ * 2, 128};
    cuuint32_t box[3] = {64, 128, 3}, es[3] = {1, 1, 1};
    fn(&P.m[4], CU_TENSOR_MAP_DATA_TYPE_BFLOAT16, 3, const_cast<__nv_bfloat16*>(P.x), dims, strides, box, es, CU_TENSOR_MAP_INTERLEAVE_NONE,
       CU_TENSOR_MAP_SWIZZLE_128B, CU_TENSOR_MAP_L2_PROMOTION_L2_256B, CU_TENSOR_MAP_FLOAT_OOB_FILL_NONE);
  }
  encode2d(fn, &P.m[5], P.x, D_, 2048, 72, 128);
  fused_block_kernel<<<128, 384, SMEM_BYTES, cudaStreamPerThread>>>(P);
}
```
